```python
import torch

def _softmax(x, axis=-1):
    return torch.softmax(x, dim=axis)
def _gelu(x):
    return torch.nn.functional.gelu(x, approximate="tanh")
def _silu(x):
    return torch.nn.functional.silu(x)
def _sigmoid(x):
    return torch.sigmoid(x)
def _layernorm(x, axis=-1, eps=1e-5):
    m = x.mean(dim=axis, keepdim=True)
    v = x.var(dim=axis, keepdim=True, unbiased=False)
    return (x - m) / torch.sqrt(v + eps)
def _scatter_add(tgt, idx, src, axis=0):
    return tgt.clone().index_add_(axis, idx, src)
def _segment_sum(src, seg, n):
    out = torch.zeros((n,) + src.shape[1:], dtype=src.dtype)
    return out.index_add_(0, seg, src)
def _pad(x, pw):
    flat = tuple(v for pair in reversed(pw) for v in pair)
    return torch.nn.functional.pad(x, flat)

kernel_name = 'interleave_layers__mha_block_cached__dense_activation_gelu__decode'

def setup_inputs():

    _w = (lambda a: (lambda t: t.to(torch.bfloat16) if t.is_floating_point() else t)(torch.as_tensor(a)))
    def _A_setup():
        B, Sq, D = 2, 1, 512
        H, Sk, Dh = 32, 8192, 128
        return {
            "x": _w((lambda *s: torch.randn(*s, dtype=torch.bfloat16) * 0.1)(B, Sq, D)),
            "k_cache": _w((lambda *s: torch.randn(*s, dtype=torch.bfloat16) * 0.8)(B, H, Sk, Dh)),
            "v_cache": _w((lambda *s: torch.randn(*s, dtype=torch.bfloat16) * 3.2)(B, H, Sk, Dh)),
            "wq": _w((lambda *s: torch.randn(*s, dtype=torch.bfloat16) * 0.8)(D, H * Dh) * (D ** -0.5)),
            "wo": _w((lambda *s: torch.randn(*s, dtype=torch.bfloat16) * 3.2)(H * Dh, D) * ((H * Dh) ** -0.5)),
        }
    _A_in = _A_setup()

    def _B_setup():
        B, S, D, F = 2, 1, 512, 1792
        return {
            "x": _w((lambda *s: torch.randn(*s, dtype=torch.bfloat16) * 0.1)(B, S, D)),
            "w1": _w((lambda *s: torch.randn(*s, dtype=torch.bfloat16) * 1.6)(D, F) * (D ** -0.5)),
            "b1": _w((lambda *s: torch.randn(*s, dtype=torch.bfloat16) * 1.6)(F) * 0.01),
            "w2": _w((lambda *s: torch.randn(*s, dtype=torch.bfloat16) * 0.4)(F, D) * (F ** -0.5)),
            "b2": _w((lambda *s: torch.randn(*s, dtype=torch.bfloat16) * 0.4)(D) * 0.01),
        }
    _B_in = _B_setup()

    return {
        "A_x": _A_in["x"],
        "A_k_cache": _A_in["k_cache"],
        "A_v_cache": _A_in["v_cache"],
        "A_wq": _A_in["wq"],
        "A_wo": _A_in["wo"],
        "B_x": _B_in["x"],
        "B_w1": _B_in["w1"],
        "B_b1": _B_in["b1"],
        "B_w2": _B_in["w2"],
        "B_b2": _B_in["b2"],
    }

def reference(A_x, A_k_cache, A_v_cache, A_wq, A_wo, B_x, B_w1, B_b1, B_w2, B_b2):
    def _A_ref(x, k_cache, v_cache, wq, wo):
        B, Sq, D = x.shape
        H, Dh = 32, 128
        q = (lambda x, *d: x.permute(*d))((x @ wq).reshape(B, Sq, H, Dh), 0, 2, 1, 3)
        scores = torch.einsum("bhqd,bhkd->bhqk", q, k_cache) * (Dh ** -0.5)
        p = _softmax(scores, axis=-1)
        o = torch.einsum("bhqk,bhkd->bhqd", p, v_cache)
        return (lambda x, *d: x.permute(*d))(o, 0, 2, 1, 3).reshape(B, Sq, H * Dh) @ wo

    def _B_ref(x, w1, b1, w2, b2):
        h = torch.einsum("bsd,df->bsf", x, w1) + b1
        h = _gelu(h)
        return torch.einsum("bsf,fd->bsd", h, w2) + b2

    x = A_x
    x = x + _A_ref(_layernorm(x, axis=-1), A_k_cache, A_v_cache, A_wq, A_wo)
    x = x + _B_ref(_layernorm(x, axis=-1), B_w1, B_b1, B_w2, B_b2)
    x = x + _A_ref(_layernorm(x, axis=-1), A_k_cache, A_v_cache, A_wq, A_wo)
    x = x + _B_ref(_layernorm(x, axis=-1), B_w1, B_b1, B_w2, B_b2)
    return x
```

```cpp
#include <cuda.h>
#include <cuda_runtime.h>
#include <cuda_bf16.h>
#include <stdint.h>

namespace {

typedef __nv_bfloat16 bf16;

constexpr int kCtas = 128;
constexpr int kSlots = 4;
constexpr int kBlk = 4096;
constexpr int kMlpCtas = 112;
constexpr int kThreads = 384;

constexpr uint32_t kHeld = 6;
constexpr uint32_t kKeep0 = 40;
constexpr uint32_t kGapWarps = 6;
constexpr uint32_t kSeg2Warps = 5;
constexpr uint32_t kEarly = 3;
constexpr uint32_t kPollDelay = 400;
constexpr uint32_t kPollGap = 200, kPollGap2 = 300;
constexpr int kRegsMain = 232, kRegsGlue = 40;

constexpr int kSmQ = 8 * kSlots * kBlk;
constexpr int kSmXs = kSmQ + 768;
constexpr int kSmBar = kSmXs + 1024;
constexpr int kBarQ = 32, kBarF = 35, kBarP = 39, kBarW = 43, kBarQ1 = 45, kNumBars = 46;
constexpr int kScLn = kSmBar + 46 * 8;
constexpr int kScR = kScLn + 32;
constexpr int kSmCnt = kScR + 64;
constexpr int kSmTag = kSmCnt + 24;
constexpr int kSmP = kSmCnt + 32;
constexpr int kSmWq = kSmP + 64;
constexpr int kSmWo = kSmWq + 32768 + 112;
constexpr int kSmW2 = kSmWo + 32768 + 112;
constexpr int kSmW1 = kSmW2 + 16384 + 112;
constexpr int kSmemBytes = kSmW1 + 16384;
static_assert(kSmemBytes <= 232448 && (kSmWq & 15) == 0, "smem");

__device__ __align__(256) uint32_t g_po[2][32][32][128];
__device__ __align__(256) uint2 g_pml[2][32][32];
__device__ __align__(256) uint32_t g_qp[2][32][4][128];
__device__ __align__(256) uint32_t g_y[2][128][512];
__device__ __align__(256) uint32_t g_x[6][512];
__device__ uint32_t g_epoch;

struct KParams {
  alignas(64) CUtensorMap vmap[2];
  const bf16 *x, *K, *V, *wq, *wo, *w1, *b1, *w2, *b2;
  bf16* out;
  uint32_t segp[7];
};

constexpr uint64_t kPolFirst = 0x12F0000000000000ull;
constexpr float kScaleLog2 = 0.08838834764831845f * 1.4426950408889634f;
constexpr uint32_t kSpinLimit = 1u << 22, kSpinClocks = 1u << 31;

__device__ __forceinline__ void mbar_init(uint32_t a, int c) {
  asm volatile("mbarrier.init.shared::cta.b64 [%0], %1;" ::"r"(a), "r"(c) : "memory");
}
__device__ __forceinline__ void mbar_expect(uint32_t a, int bytes) {
  asm volatile("mbarrier.arrive.expect_tx.shared::cta.b64 _, [%0], %1;" ::"r"(a), "r"(bytes) : "memory");
}
__device__ __forceinline__ void mbar_arrive(uint32_t a) {
  asm volatile("mbarrier.arrive.shared::cta.b64 _, [%0];" ::"r"(a) : "memory");
}
__device__ __forceinline__ bool mbar_try(uint32_t a, uint32_t ph) {
  uint32_t ok;
  asm volatile("{.reg .pred p; mbarrier.try_wait.parity.shared::cta.b64 p, [%1], %2; selp.u32 %0, 1, 0, p;}"
               : "=r"(ok) : "r"(a), "r"(ph) : "memory");
  return ok != 0;
}
__device__ __forceinline__ bool mbar_test(uint32_t a, uint32_t ph) {
  uint32_t ok;
  asm volatile("{.reg .pred p; mbarrier.test_wait.parity.shared::cta.b64 p, [%1], %2; selp.u32 %0, 1, 0, p;}"
               : "=r"(ok) : "r"(a), "r"(ph) : "memory");
  return ok != 0;
}
__device__ __forceinline__ uint32_t clock32() {
  uint32_t t;
  asm volatile("mov.u32 %0, %%clock;" : "=r"(t));
  return t;
}
__device__ __forceinline__ void mbar_wait(uint32_t a, uint32_t ph) {
  if (mbar_try(a, ph)) return;
  const uint32_t t0 = clock32();
#pragma unroll 1
  while (!mbar_try(a, ph)) {
    if (clock32() - t0 > kSpinClocks) __trap();
  }
}
__device__ __forceinline__ void bulk_load(uint32_t dst, const void* src, int bytes, uint32_t bar, uint64_t pol) {
  asm volatile("cp.async.bulk.shared::cluster.global.mbarrier::complete_tx::bytes.L2::cache_hint [%0], [%1], %2, [%3], %4;"
               ::"r"(dst), "l"(src), "r"(bytes), "r"(bar), "l"(pol) : "memory");
}
__device__ __forceinline__ void tensor_load(uint32_t dst, const CUtensorMap* map, uint32_t blk, uint32_t bar) {
  asm volatile("cp.async.bulk.tensor.4d.shared::cluster.global.mbarrier::complete_tx::bytes.L2::cache_hint [%0], [%1, {%2, %2, %2, %3}], [%4], %5;"
               ::"r"(dst), "l"(map), "r"(0), "r"(blk), "r"(bar), "l"(kPolFirst) : "memory");
}
__device__ __forceinline__ void cp16(uint32_t dst, const void* src) {
  asm volatile("cp.async.cg.shared.global [%0], [%1], 16;" ::"r"(dst), "l"(src) : "memory");
}
__device__ __forceinline__ void ldsm4(uint32_t* r, uint32_t a) {
  asm volatile("ldmatrix.sync.aligned.m8n8.x4.shared.b16 {%0,%1,%2,%3}, [%4];"
               : "=r"(r[0]), "=r"(r[1]), "=r"(r[2]), "=r"(r[3]) : "r"(a) : "memory");
}
__device__ __forceinline__ void ldsm4t(uint32_t* r, uint32_t a) {
  asm volatile("ldmatrix.sync.aligned.m8n8.x4.trans.shared.b16 {%0,%1,%2,%3}, [%4];"
               : "=r"(r[0]), "=r"(r[1]), "=r"(r[2]), "=r"(r[3]) : "r"(a) : "memory");
}
__device__ __forceinline__ void mma16816(float* c, const uint32_t* a, uint32_t b0, uint32_t b1) {
  asm volatile("mma.sync.aligned.m16n8k16.row.col.f32.bf16.bf16.f32 {%0,%1,%2,%3}, {%4,%5,%6,%7}, {%8,%9}, {%0,%1,%2,%3};"
               : "+f"(c[0]), "+f"(c[1]), "+f"(c[2]), "+f"(c[3])
               : "r"(a[0]), "r"(a[1]), "r"(a[2]), "r"(a[3]), "r"(b0), "r"(b1));
}
__device__ __forceinline__ uint32_t lds32(uint32_t a) {
  uint32_t v;
  asm volatile("ld.shared.b32 %0, [%1];" : "=r"(v) : "r"(a) : "memory");
  return v;
}
__device__ __forceinline__ uint2 lds64(uint32_t a) {
  uint2 v;
  asm volatile("ld.shared.v2.b32 {%0,%1}, [%2];" : "=r"(v.x), "=r"(v.y) : "r"(a) : "memory");
  return v;
}
__device__ __forceinline__ uint4 lds128(uint32_t a) {
  uint4 v;
  asm volatile("ld.shared.v4.b32 {%0,%1,%2,%3}, [%4];" : "=r"(v.x), "=r"(v.y), "=r"(v.z), "=r"(v.w) : "r"(a) : "memory");
  return v;
}
__device__ __forceinline__ void sts32f(uint32_t a, float v) {
  asm volatile("st.shared.f32 [%0], %1;" ::"r"(a), "f"(v) : "memory");
}
__device__ __forceinline__ void sts64(uint32_t a, uint32_t x, uint32_t y) {
  asm volatile("st.shared.v2.b32 [%0], {%1,%2};" ::"r"(a), "r"(x), "r"(y) : "memory");
}
__device__ __forceinline__ float ex2(float x) {
  float y;
  asm("ex2.approx.ftz.f32 %0, %1;" : "=f"(y) : "f"(x));
  return y;
}
__device__ __forceinline__ float bf_lo(uint32_t u) { return __uint_as_float(u << 16); }
__device__ __forceinline__ float bf_hi(uint32_t u) { return __uint_as_float(u & 0xffff0000u); }
__device__ __forceinline__ float bf_round(float x) { return __bfloat162float(__float2bfloat16_rn(x)); }
__device__ __forceinline__ uint32_t bf_pack(float lo, float hi) {
  uint32_t r;
  asm("cvt.rn.bf16x2.f32 %0, %1, %2;" : "=r"(r) : "f"(hi), "f"(lo));
  return r;
}
__device__ __forceinline__ uint32_t tagged(float v, uint32_t tag) { return (__float_as_uint(v) & ~7u) | tag; }
__device__ __forceinline__ void st_rlx(uint32_t* p, uint32_t v) {
  asm volatile("st.relaxed.gpu.global.b32 [%0], %1;" ::"l"(p), "r"(v) : "memory");
}
__device__ __forceinline__ void st_rlx4(uint32_t* p, uint32_t a, uint32_t b, uint32_t c, uint32_t d) {
  asm volatile("st.relaxed.gpu.global.v4.b32 [%0], {%1,%2,%3,%4};" ::"l"(p), "r"(a), "r"(b), "r"(c), "r"(d) : "memory");
}
__device__ __forceinline__ void st_rlx2(uint2* p, uint32_t a, uint32_t b) {
  asm volatile("st.relaxed.gpu.global.v2.b32 [%0], {%1,%2};" ::"l"(p), "r"(a), "r"(b) : "memory");
}
__device__ __forceinline__ uint32_t ld_rlx(const uint32_t* p) {
  uint32_t v;
  asm volatile("ld.relaxed.gpu.global.b32 %0, [%1];" : "=r"(v) : "l"(p) : "memory");
  return v;
}
__device__ __forceinline__ uint2 ld_rlx2(const uint2* p) {
  uint2 v;
  asm volatile("ld.relaxed.gpu.global.v2.b32 {%0,%1}, [%2];" : "=r"(v.x), "=r"(v.y) : "l"(p) : "memory");
  return v;
}
__device__ __forceinline__ uint4 ld_rlx4(const uint32_t* p) {
  uint4 v;
  asm volatile("ld.relaxed.gpu.global.v4.b32 {%0,%1,%2,%3}, [%4];" : "=r"(v.x), "=r"(v.y), "=r"(v.z), "=r"(v.w) : "l"(p) : "memory");
  return v;
}
__device__ __forceinline__ uint32_t stale4(const uint4 v, uint32_t tag) {
  return ((v.x ^ tag) | (v.y ^ tag) | (v.z ^ tag) | (v.w ^ tag)) & 7u;
}
__device__ __forceinline__ float4 poll4(const uint32_t* p, uint32_t tag, uint32_t live) {
  uint4 v = make_uint4(0, 0, 0, 0);
  if (live) {
    const uint32_t t0 = clock32();
    while (clock32() - t0 < kPollDelay) {}
  }
#pragma unroll 1
  for (uint32_t n = 0; live; n++) {
    v = ld_rlx4(p);
    if (!stale4(v, tag)) break;
    if (n > kSpinLimit) __trap();
    if (live > 1) __nanosleep(live);
  }
  return make_float4(__uint_as_float(v.x), __uint_as_float(v.y), __uint_as_float(v.z), __uint_as_float(v.w));
}
__device__ __forceinline__ void glue_bar() { asm volatile("bar.sync 1, 128;" ::: "memory"); }

struct MainCtx {
  uint32_t ko;
  uint32_t st;
  uint32_t sp;
};
__device__ __forceinline__ uint32_t laneid() {
  uint32_t t;
  asm volatile("mov.u32 %0, %%laneid;" : "=r"(t));
  return t;
}
__device__ __forceinline__ bool elect() {
  uint32_t ok;
  asm volatile("{.reg .pred p; elect.sync _|p, 0xffffffff; selp.u32 %0, 1, 0, p;}" : "=r"(ok) :: "memory");
  return ok != 0;
}
__device__ __forceinline__ uint32_t seg_of(const MainCtx& c) { return (c.st >> 9) & 7; }
__device__ __forceinline__ uint32_t job_of(const MainCtx& c) { return c.st >> 16; }
__device__ __forceinline__ void set_job(MainCtx& c, uint32_t e) { c.st = (c.st & 0xffffu) | (e << 16); }
__device__ __forceinline__ uint32_t q_addr(const MainCtx& c, uint32_t smem) {
  return smem + kSmQ + laneid() * 8 + ((0x021210u >> (seg_of(c) * 4)) & 3) * 256;
}
__device__ __forceinline__ uint32_t k_addr(const MainCtx& c, uint32_t smem, uint32_t slot) {
  return smem + (c.ko ^ (c.st & 0x8000u)) + slot * kBlk;
}
__device__ __forceinline__ uint32_t v_addr(const MainCtx& c, uint32_t smem, uint32_t slot) {
  const uint32_t lane = laneid();
  return smem + ((c.ko ^ (c.st & 0x8000u)) & 0x1c000u) + slot * kBlk + (lane >> 4) * 1024 + (lane & 7) * 128 + ((((lane >> 3) ^ lane) & 1) | (lane & 6)) * 16;
}
__device__ __forceinline__ uint32_t bar_addr(const MainCtx& c, uint32_t smem, uint32_t slot) {
  return smem + kSmBar + (((c.ko ^ (c.st & 0x8000u)) >> 14) * kSlots + slot) * 8;
}
template <bool ISV>
__device__ __forceinline__ void issue(const KParams& P, const MainCtx& c, uint32_t smem, uint32_t slot, uint32_t e) {
  const uint32_t x = ((c.ko ^ (c.st & 0x8000u)) & 0x1c000u) + slot * kBlk;
  if (elect()) {
    const uint32_t bar = smem + kSmBar + (x >> 9), bytes = kBlk + ((e >> 3) & kBlk);
    const uint32_t off = (blockIdx.x << 19) + ((e & 0x407fu) << 12);
    const char* src = (const char*)(ISV ? P.V : P.K) + off;
    mbar_expect(bar, bytes);
    if (ISV) tensor_load(smem + x, &P.vmap[(e >> 15) & 1], off >> 12, bar);
    else bulk_load(smem + x, src, bytes, bar, kPolFirst);
    if (e & 0x100u) asm volatile("cp.async.bulk.commit_group; cp.async.bulk.prefetch.L2.global [%0], %1;" ::"l"(src), "n"(kBlk) : "memory");
  }
}
__device__ __forceinline__ void wait_slot(MainCtx& c, uint32_t smem, uint32_t slot) {
  mbar_wait(bar_addr(c, smem, slot), (c.st >> slot) & 1);
  c.st ^= 1u << slot;
}
__device__ __forceinline__ void issue_v(const KParams& P, MainCtx& c, uint32_t smem) {
  if (c.st & 16u) {
    issue<true>(P, c, smem, 2, job_of(c));
    c.st &= ~16u;
  }
}
template <bool ISV>
__device__ __forceinline__ void reload_kept(const KParams& P, const MainCtx& c, uint32_t smem) {
  if (seg_of(c) == 2 && !(c.st >> 31)) issue<ISV>(P, c, smem, ISV ? 3 : 1, (24 + ((c.ko ^ (c.st & 0x8000u)) >> 14)) | 0x4000u);
}
__device__ __forceinline__ uint32_t ticket(const MainCtx& c, uint32_t smem) {
  uint32_t u = 255;
  if (laneid() == 0 && (c.st & 0x180u) == 0x180u && (c.sp & 0x7f0000u)) {
    const uint32_t lseg = (c.sp >> 11) & 7;
    if (lseg != 1 || !mbar_test(smem + kSmBar + (kBarQ + 1) * 8, 0))
      asm volatile("atom.shared.add.u32 %0, [%1], 1;" : "=r"(u) : "r"(smem + kSmCnt + (lseg == 3 ? 1 : lseg) * 4) : "memory");
  }
  return u;
}
__device__ __forceinline__ bool pick(const KParams& P, MainCtx& c, uint32_t smem, uint32_t u) {
  bool hask = true;
#pragma unroll 1
  while (true) {
    u = __shfl_sync(0xffffffffu, u, 0);
    const uint32_t lim = (c.sp >> 16) & 0x7f;
    if (u < lim) {
      uint32_t e = (c.sp & 0xf87fu) + u;
      if (c.sp & 0x8000u) {
        const uint32_t v = u & ~1u;
        e = (u & 1) ? (c.sp & 0xf800u) + 126 - v : (c.sp & 0xf87fu) + v;
        u *= 2;
      }
      if (u >= (c.sp >> 24)) e |= 0x100u;
      if (u + 8 * kEarly >= ((c.sp & 0x8000u) ? 2 * lim : lim)) e |= 0x80u;
      set_job(c, e);
      break;
    }
    const uint32_t w = (c.ko ^ (c.st & 0x8000u)) >> 14, lseg = (c.sp >> 11) & 7, lstep = (c.st >> 7) & 3;
    if (lstep < 3) {
      set_job(c, (lstep * 8 + w) | (c.sp & 0x7800u));
      c.st += 1u << 7;
      break;
    }
    if (lseg == 6) { set_job(c, 0); hask = false; break; }
    c.sp = P.segp[lseg + 1];
    if (w >= ((lseg == 0 || lseg == 3) ? kGapWarps : (lseg == 1 ? kSeg2Warps : 8))) c.sp &= ~0x7f0000u;
    if (lseg == 2) c.st &= ~0x180u;
    u = ticket(c, smem);
  }
  return hask;
}

template <int MODE>
__device__ __forceinline__ void qk_block(float* s, uint32_t* rf, uint32_t ka, uint32_t qa) {
  float t[4];
  s[0] = s[1] = s[2] = s[3] = t[0] = t[1] = t[2] = t[3] = 0.f;
#pragma unroll
  for (int st = 0; st < 8; st++) {
    uint32_t a[4];
    uint32_t* f = MODE == 0 ? a : rf + 4 * st;
    if (MODE != 2) ldsm4(f, ka ^ (st << 4));
    const uint2 b = lds64(qa ^ (st << 5));
    mma16816((st & 1) ? t : s, f, b.x, b.y);
  }
  s[0] += t[0]; s[1] += t[1]; s[2] += t[2]; s[3] += t[3];
}
__device__ __forceinline__ void qk_wide(float* s, uint32_t ka, uint32_t qa) {
#pragma unroll
  for (int i = 0; i < 8; i++) s[i] = 0.f;
#pragma unroll
  for (int st = 0; st < 8; st++) {
    uint32_t a[8];
    ldsm4(a, ka ^ (st << 4));
    ldsm4(a + 4, (ka + kBlk) ^ (st << 4));
    const uint2 b = lds64(qa ^ (st << 5));
    mma16816(s, a, b.x, b.y);
    mma16816(s + 4, a + 4, b.x, b.y);
  }
}
template <int MODE>
__device__ __forceinline__ void pv_block(float* acc, uint32_t* rf, uint32_t va, uint32_t b0, uint32_t b1) {
  const uint32_t g = laneid() >> 2;
#pragma unroll
  for (int h = 0; h < 2; h++) {
    uint32_t a[16];
    uint32_t* f = MODE == 0 ? a : rf + 16 * h;
#pragma unroll
    for (int i = 0; i < 4; i++)
      if (MODE != 2) ldsm4t(f + 4 * i, (va ^ (i << 5)) + h * 2048);
#pragma unroll
    for (int i = 0; i < 4; i++) {
      const bool on = g == (uint32_t)(4 * h + i);
      mma16816(acc, f + 4 * i, on ? b0 : 0u, on ? b1 : 0u);
    }
  }
}
template <int NB>
__device__ __forceinline__ void softmax_block(const float* s, float* acc, float& m, float& l, uint32_t* b) {
  const uint32_t lane = laneid(), g = lane >> 2, t = lane & 3;
  const bool valid = (t == (g >> 1));
  const bool odd = g & 1;
  const float ninf = __int_as_float(0xff800000);
  float v[2 * NB];
#pragma unroll
  for (int i = 0; i < 2 * NB; i++) v[i] = valid ? (odd ? s[2 * i + 1] : s[2 * i]) : ninf;
  float bm = fmaxf(v[0], v[1]);
  if (NB == 2) bm = fmaxf(bm, fmaxf(v[2 * NB - 2], v[2 * NB - 1]));
  if (__any_sync(0xffffffffu, bm > m)) {
#pragma unroll
    for (int o = 16; o > 0; o >>= 1) bm = fmaxf(bm, __shfl_xor_sync(0xffffffffu, bm, o));
    const float mn = fmaxf(m, bm);
    const float sc = ex2((m - mn) * kScaleLog2);
    m = mn;
    l *= sc;
    acc[0] *= sc; acc[1] *= sc; acc[2] *= sc; acc[3] *= sc;
  }
#pragma unroll
  for (int i = 0; i < NB; i++) {
    const float p0 = ex2((v[2 * i] - m) * kScaleLog2), p1 = ex2((v[2 * i + 1] - m) * kScaleLog2);
    l += p0 + p1;
    const uint32_t pk = bf_pack(p0, p1);
    const uint32_t x = __shfl_sync(0xffffffffu, pk, 9 * t), y = __shfl_sync(0xffffffffu, pk, 9 * t + 4);
    b[2 * i] = __byte_perm(x, y, 0x5410);
    b[2 * i + 1] = __byte_perm(x, y, 0x7632);
  }
}

template <bool LAST>
__device__ __forceinline__ void load_job(const KParams& P, MainCtx& c, uint32_t smem, float* acc, float& m, float& l,
                                         uint32_t* rf) {
  float s[4];
  uint32_t b[2];
  const uint32_t u = LAST ? ticket(c, smem) : 0u;
  wait_slot(c, smem, 0);
  issue_v(P, c, smem);
  qk_block<1>(s, rf, k_addr(c, smem, 0), q_addr(c, smem));
  bool hask = true;
  if (LAST) hask = pick(P, c, smem, u) && !(c.st >> 31);
  else c.st += (8u << 16) + (1u << 7);
  softmax_block<1>(s, acc, m, l, b);
  wait_slot(c, smem, 2);
  if (hask) issue<false>(P, c, smem, 0, job_of(c));
  pv_block<1>(acc, rf + 32, v_addr(c, smem, 2), b[0], b[1]);
  if (hask) c.st |= 16u;
}
__device__ __forceinline__ void reuse_job(MainCtx& c, uint32_t smem, float* acc, float& m, float& l, uint32_t* rf) {
  float s[4];
  uint32_t b[2];
  qk_block<2>(s, rf, 0, q_addr(c, smem));
  softmax_block<1>(s, acc, m, l, b);
  pv_block<2>(acc, rf + 32, 0, b[0], b[1]);
}
__device__ __forceinline__ void ring_job(const KParams& P, MainCtx& c, uint32_t smem, float* acc, float& m, float& l) {
  float s[4];
  uint32_t b[2];
  const uint32_t kept = (c.st >> 5) & 3, p = kept != 0, seg = seg_of(c);
  const bool lazy = seg == 1 || seg == 4;
  const uint32_t u = kept ? 255u : ticket(c, smem);
  if (kept == 2) c.st ^= 10u;
  if (lazy) wait_slot(c, smem, p);
  issue_v(P, c, smem);
  if (!lazy) wait_slot(c, smem, p);
  qk_block<0>(s, nullptr, k_addr(c, smem, p), q_addr(c, smem));
  bool hask = kept == 2 && (c.st >> 31);
  if (!kept) hask = pick(P, c, smem, u) && !(c.st >> 31);
  if (kept == 2) reload_kept<false>(P, c, smem);
  softmax_block<1>(s, acc, m, l, b);
  if (lazy) wait_slot(c, smem, 2 + p);
  if (hask) issue<false>(P, c, smem, 0, job_of(c));
  if (!lazy) wait_slot(c, smem, 2 + p);
  pv_block<0>(acc, nullptr, v_addr(c, smem, 2 + p), b[0], b[1]);
  if (hask) c.st |= 16u;
}
__device__ __forceinline__ void wide_job(const KParams& P, MainCtx& c, uint32_t smem, float* acc, float& m, float& l) {
  float s[8];
  uint32_t b[4];
  const uint32_t u = ticket(c, smem);
  wait_slot(c, smem, 0);
  issue_v(P, c, smem);
  qk_wide(s, k_addr(c, smem, 0), q_addr(c, smem));
  const bool hask = pick(P, c, smem, u);
  reload_kept<false>(P, c, smem);
  softmax_block<2>(s, acc, m, l, b);
  wait_slot(c, smem, 2);
  if (hask) issue<false>(P, c, smem, 0, job_of(c));
  pv_block<0>(acc, nullptr, v_addr(c, smem, 2), b[0], b[1]);
  pv_block<0>(acc, nullptr, v_addr(c, smem, 3), b[2], b[3]);
  if (hask) c.st |= 16u;
  reload_kept<true>(P, c, smem);
}

__device__ __forceinline__ uint32_t warp_of() {
  uint32_t t;
  asm volatile("mov.u32 %0, %%tid.x;" : "=r"(t));
  return t >> 5;
}
__device__ __forceinline__ uint32_t* part_o(int fs, uint32_t lane) {
  return &g_po[fs][0][0][0] + (blockIdx.x * 8 + warp_of()) * 128 + ((lane & 3) * 8 + (lane >> 2)) * 4;
}
__device__ __forceinline__ uint2* part_ml(int fs) { return &g_pml[fs][0][0] + blockIdx.x * 8 + warp_of(); }
__device__ __forceinline__ void flush(float* acc, float m, float l, int fs, uint32_t tag) {
  const uint32_t lane = laneid();
  st_rlx4(part_o(fs, lane), tagged(acc[0], tag), tagged(acc[2], tag), tagged(acc[1], tag), tagged(acc[3], tag));
#pragma unroll
  for (int o = 16; o > 0; o >>= 1) l += __shfl_xor_sync(0xffffffffu, l, o);
  if (lane == 0) st_rlx2(part_ml(fs), tagged(m, tag), tagged(l, tag));
}
__device__ __forceinline__ void restore(float* acc, float& m, float& l, int fs) {
  const uint32_t lane = laneid();
  const uint4 o = ld_rlx4(part_o(fs, lane));
  const uint2 ml = ld_rlx2(part_ml(fs));
  acc[0] = __uint_as_float(o.x);
  acc[2] = __uint_as_float(o.y);
  acc[1] = __uint_as_float(o.z);
  acc[3] = __uint_as_float(o.w);
  m = __uint_as_float(ml.x);
  l = lane == 0 ? __uint_as_float(ml.y) : 0.f;
}

__device__ __forceinline__ void main_role(const KParams& P, uint32_t smem) {
  MainCtx c;
  {
    const uint32_t w = threadIdx.x >> 5, mi = (threadIdx.x >> 3) & 3, i = threadIdx.x & 7;
    c.ko = w * kSlots * kBlk + ((mi & 1) * 8 + i) * 256 + (mi >> 1) * 128 + i * 16;
    c.st = (1u << 7) | (w << 16);
    c.sp = P.segp[0];
#pragma unroll 1
    for (uint32_t s = 1; s < 4; s++) {
      mbar_wait(bar_addr(c, smem, ((s - 1) >> 1) | (((s - 1) & 1) << 1)), 0);
      if (s & 1) issue<true>(P, c, smem, 2 + (s >> 1), w + (s >> 1) * 24);
      else issue<false>(P, c, smem, 1, w + 24);
    }
  }

  float acc[4];
  uint32_t rf[192];
  float m = -3.0e38f, l = 0.f;
  acc[0] = acc[1] = acc[2] = acc[3] = 0.f;

#pragma unroll 1
  for (; seg_of(c) < 6; c.st = (c.st & ~0x1000u) + 0x200u) {
    {
      const uint32_t seg = seg_of(c);
      if (seg < 2) mbar_wait(smem + kSmBar + (seg ? kBarQ1 : kBarQ) * 8, 0);
      if (seg == 3 || seg == 4) restore(acc, m, l, seg & 1);
      if (seg == 0 || seg == 3) {
        load_job<false>(P, c, smem, acc, m, l, rf);
        load_job<false>(P, c, smem, acc, m, l, rf + 64);
        load_job<true>(P, c, smem, acc, m, l, rf + 128);
        c.st |= 1u << 5;
      } else if (seg == 2 || seg == 5) {
        issue_v(P, c, smem);
        mbar_wait(smem + kSmBar + (kBarQ + (seg_of(c) == 2 ? 1 : 2)) * 8, 0);
        c.st |= 2u << 5;
      }
    }
    if (seg_of(c) == 1 || seg_of(c) == 2) c.st |= 0x1000u;
#pragma unroll 1
    while (true) {
#pragma unroll 1
      while (true) {
        const uint32_t kept = (c.st >> 5) & 3;
        if (!kept && ((((c.st >> 27) ^ (c.st >> 9)) & 7) != 0 || (c.st & 0x801000u) == 0x800000u)) break;
        if (!kept && (c.st >> 31)) {
          wide_job(P, c, smem, acc, m, l);
        } else {
          ring_job(P, c, smem, acc, m, l);
          if (c.st & (2u << 5)) {
            reload_kept<true>(P, c, smem);
            issue_v(P, c, smem);
            reuse_job(c, smem, acc, m, l, rf);
            reuse_job(c, smem, acc, m, l, rf + 64);
            reuse_job(c, smem, acc, m, l, rf + 128);
          }
          c.st &= ~(3u << 5);
        }
      }
      const uint32_t tag = lds32(smem + kSmTag);
      c.st |= tag & 0x8000u;
      const uint32_t seg = seg_of(c), half = (c.st >> 12) & 1;
      const bool pub = seg == 0 || seg >= 3;
      flush(acc, m, l, seg & 1, (tag ^ ((pub && half) ? 0u : 4u)) | (seg >> 2));
      __syncwarp();
      if (pub && laneid() == 0) mbar_arrive(smem + kSmBar + ((half ? kBarF : kBarP) + (seg ? seg - 2 : 0)) * 8);
      if (half) break;
      c.st |= 0x1000u;
    }
    acc[0] = acc[1] = acc[2] = acc[3] = 0.f;
    m = -3.0e38f;
    l = 0.f;
  }
}

__device__ __forceinline__ uint32_t gtid() {
  uint32_t t;
  asm volatile("mov.u32 %0, %%tid.x;" : "=r"(t));
  return t - 256;
}
__device__ __forceinline__ uint32_t gcta() {
  uint32_t t;
  asm volatile("mov.u32 %0, %%ctaid.x;" : "=r"(t));
  return t;
}
__device__ __forceinline__ void stats_put(const float4 x, uint32_t smem) {
  const uint32_t tid = gtid();
  const float pv = __shfl_sync(0xffffffffu, x.x, 0);
  const float d0 = x.x - pv, d1 = x.y - pv, d2 = x.z - pv, d3 = x.w - pv;
  float s1 = (d0 + d1) + (d2 + d3), s2 = (d0 * d0 + d1 * d1) + (d2 * d2 + d3 * d3);
#pragma unroll
  for (int o = 16; o > 0; o >>= 1) {
    s1 += __shfl_xor_sync(0xffffffffu, s1, o);
    s2 += __shfl_xor_sync(0xffffffffu, s2, o);
  }
  if ((tid & 31) == 0)
    sts64(smem + kScLn + (tid >> 5) * 8, __float_as_uint(pv + s1 * (1.f / 128.f)), __float_as_uint(fmaxf(s2 - s1 * s1 * (1.f / 128.f), 0.f)));
}
__device__ __forceinline__ float2 stats_get(uint32_t smem) {
  const uint4 a = lds128(smem + kScLn), b = lds128(smem + kScLn + 16);
  const float m0 = __uint_as_float(a.x), m1 = __uint_as_float(a.z), m2 = __uint_as_float(b.x), m3 = __uint_as_float(b.z);
  const float mean = 0.25f * ((m0 + m1) + (m2 + m3));
  const float m2s = (__uint_as_float(a.y) + __uint_as_float(a.w)) + (__uint_as_float(b.y) + __uint_as_float(b.w)) +
                    128.f * ((m0 - mean) * (m0 - mean) + (m1 - mean) * (m1 - mean) + (m2 - mean) * (m2 - mean) +
                             (m3 - mean) * (m3 - mean));
  float rstd;
  asm("rsqrt.approx.ftz.f32 %0, %1;" : "=f"(rstd) : "f"(m2s * (1.f / 512.f) + 1e-5f));
  return make_float2(mean, rstd);
}
__device__ __forceinline__ float4 unpack4(const uint2 v) { return make_float4(bf_lo(v.x), bf_hi(v.x), bf_lo(v.y), bf_hi(v.y)); }
__device__ __forceinline__ uint2 pack4(const float4 v) { return make_uint2(bf_pack(v.x, v.y), bf_pack(v.z, v.w)); }
__device__ __forceinline__ void sts16(uint32_t a, uint32_t v) {
  asm volatile("st.shared.u16 [%0], %1;" ::"r"(a), "h"((unsigned short)v) : "memory");
}
__device__ __forceinline__ uint32_t col0(uint32_t j) { return (j >> 5) * 128 + (j & 3) * 32 + ((j >> 2) & 7); }
__device__ __forceinline__ float sel4(uint32_t t, float a, float b, float c, float d) {
  return (t & 2) ? ((t & 1) ? d : c) : ((t & 1) ? b : a);
}
constexpr uint32_t kOnes = 0x3f803f80u;
__device__ __forceinline__ void q_stage(const float4 x, uint32_t smem, uint32_t qi, uint32_t tag, uint32_t live) {
  {
    const uint32_t tid = gtid();
    if ((tid >> 5) == (gcta() & 3)) {
      const uint32_t a = smem + kSmXs + ((tid >> 2) & 7) * 16 + (tid & 3) * 4;
      sts16(a, __float_as_uint(x.x) >> 16); sts16(a + 128, __float_as_uint(x.y) >> 16);
      sts16(a + 2, __float_as_uint(x.z) >> 16); sts16(a + 130, __float_as_uint(x.w) >> 16);
    }
  }
  stats_put(x, smem);
  glue_bar();
  {
    const uint32_t tid = gtid(), ww = tid >> 5, lane = tid & 31, mi = lane >> 3, i = lane & 7, t = lane & 3;
    const uint32_t wa = smem + kSmWq + i * (4096 + 16) + (mi >> 1) * 256 + (ww * 4 + (mi & 1)) * 16;
    const uint32_t xa = smem + kSmXs + t * 4;
    const bool odd = lane & 4;
    float c[2][4];
#pragma unroll
    for (int k = 0; k < 4; k++) c[0][k] = c[1][k] = 0.f;
#pragma unroll
    for (int ks = 0; ks < 8; ks++) {
      const uint32_t b0 = lds32(xa + ks * 32), b1 = lds32(xa + ks * 32 + 16);
      uint32_t a0[4], a1[4];
      ldsm4t(a0, wa + ks * 512);
      ldsm4t(a1, wa + ks * 512 + 32);
      mma16816(c[0], a0, odd ? kOnes : b0, odd ? kOnes : b1);
      mma16816(c[1], a1, odd ? kOnes : b0, odd ? kOnes : b1);
    }
    const float2 st = stats_get(smem);
    tag |= qi >> 1;
    st_rlx(&g_qp[qi & 1][0][0][0] + gcta() * 128 + ww * 32 + t * 8 + (lane >> 2),
           tagged(st.y * (sel4(t, c[0][0], c[0][2], c[1][0], c[1][2]) - st.x * sel4(t, c[0][1], c[0][3], c[1][1], c[1][3])), tag));
  }
  const uint32_t tid = gtid();
  const uint32_t* src = &g_qp[qi & 1][0][0][0] + (gcta() >> 2) * 512 + tid;
  uint4 v = make_uint4(0, 0, 0, 0);
  if (live) {
    const uint32_t t0 = clock32();
    while (clock32() - t0 < kPollDelay) {}
  }
#pragma unroll 1
  for (uint32_t n = 0; live; n++) {
    v.x = ld_rlx(src); v.y = ld_rlx(src + 128); v.z = ld_rlx(src + 256); v.w = ld_rlx(src + 384);
    if (!stale4(v, tag)) break;
    if (n > kSpinLimit) __trap();
    if (live > 1) __nanosleep(live);
  }
  const float r = (__uint_as_float(v.x) + __uint_as_float(v.y)) + (__uint_as_float(v.z) + __uint_as_float(v.w));
  const uint32_t hf = tid >> 6, ck = (tid >> 3) & 7, k = tid & 7;
  sts16(smem + kSmQ + (qi == 3 ? 0 : qi) * 256 + (ck * 4 + (k >> 1)) * 8 + hf * 4 + (k & 1) * 2, bf_pack(r, 0.f));
  glue_bar();
}
template <int KS>
__device__ __forceinline__ void wide_mma(uint32_t wbase, const uint32_t* b, uint32_t yi, uint32_t tag) {
  const uint32_t tid = gtid(), ww = tid >> 5, lane = tid & 31, mi = lane >> 3, i = lane & 7, g = lane >> 2;
  const uint32_t wa = wbase + i * (KS * 2048 + 16) + (mi >> 1) * 1024 + ww * 256 + (mi & 1) * 16;
  float c[2][4];
#pragma unroll
  for (int k = 0; k < 4; k++) c[0][k] = c[1][k] = 0.f;
#pragma unroll
  for (int j = 0; j < 8; j += 3 - KS) {
    uint32_t a0[4], a1[4];
    ldsm4t(a0, wa + j * 32);
    ldsm4t(a1, wa + j * 32 + (KS == 2 ? 2048 : 32));
    const bool on0 = (g == (uint32_t)j), on1 = (g == (uint32_t)(KS == 2 ? j : j + 1));
    mma16816(c[0], a0, on0 ? b[0] : 0u, on0 ? b[1] : 0u);
    mma16816(c[1], a1, on1 ? b[2 * KS - 2] : 0u, on1 ? b[2 * KS - 1] : 0u);
  }
  st_rlx4(&g_y[yi][0][0] + gcta() * 512 + tid * 4, tagged(c[0][0] + c[1][0], tag), tagged(c[0][2] + c[1][2], tag),
          tagged(c[0][1] + c[1][1], tag), tagged(c[0][3] + c[1][3], tag));
}
__device__ __forceinline__ float4 reduce_cols(uint32_t yi, uint32_t nsrc, uint32_t smem, uint32_t tag, uint32_t live) {
  const uint32_t tid = gtid();
  const float4 v = poll4(&g_y[yi][0][0] + tid * 512 + gcta() * 4, tag, tid < nsrc ? live : 0u);
  __syncwarp();
  const bool u16 = tid & 16, u8 = tid & 8;
  const float a = (u16 ? v.z : v.x) + __shfl_xor_sync(0xffffffffu, u16 ? v.x : v.z, 16);
  const float b = (u16 ? v.w : v.y) + __shfl_xor_sync(0xffffffffu, u16 ? v.y : v.w, 16);
  float r = (u8 ? b : a) + __shfl_xor_sync(0xffffffffu, u8 ? a : b, 8);
  r += __shfl_xor_sync(0xffffffffu, r, 4);
  r += __shfl_xor_sync(0xffffffffu, r, 2);
  r += __shfl_xor_sync(0xffffffffu, r, 1);
  if ((tid & 7) == 0) sts32f(smem + kScR + (tid >> 3) * 4, r);
  glue_bar();
  const uint4 p0 = lds128(smem + kScR), p1 = lds128(smem + kScR + 16), p2 = lds128(smem + kScR + 32), p3 = lds128(smem + kScR + 48);
  return make_float4((__uint_as_float(p0.x) + __uint_as_float(p1.x)) + (__uint_as_float(p2.x) + __uint_as_float(p3.x)),
                     (__uint_as_float(p0.y) + __uint_as_float(p1.y)) + (__uint_as_float(p2.y) + __uint_as_float(p3.y)),
                     (__uint_as_float(p0.z) + __uint_as_float(p1.z)) + (__uint_as_float(p2.z) + __uint_as_float(p3.z)),
                     (__uint_as_float(p0.w) + __uint_as_float(p1.w)) + (__uint_as_float(p2.w) + __uint_as_float(p3.w)));
}
__device__ __forceinline__ float4 poll_x(uint32_t xi, uint32_t tag, uint32_t live) {
  const float4 x = poll4(&g_x[xi][0] + gtid() * 4, tag, live);
  return make_float4(bf_round(x.x), bf_round(x.y), bf_round(x.z), bf_round(x.w));
}

__device__ __forceinline__ float gelu_tanh(float x) {
  const float u = 0.7978845608028654f * (x + 0.044715f * x * x * x);
  return __fdividef(x, 1.0f + ex2(-2.8853900817779268f * u));
}

__device__ __forceinline__ void combine(uint32_t* bo, uint32_t smem, uint32_t fs, uint32_t tag, uint32_t live) {
  const uint32_t tid = gtid(), lane = tid & 31, cta = gcta(), pg = tid >> 3;
  const uint2* pm = &g_pml[fs][0][0] + (cta >> 2) * 32 + lane;
  const uint32_t* pa = &g_po[fs][0][0][0] + ((cta >> 2) * 32 + pg) * 128 + (cta & 3) * 32 + (tid & 7) * 4;
  uint2 ml = make_uint2(0, 0);
  uint4 a0 = make_uint4(0, 0, 0, 0), a1 = a0;
#pragma unroll 1
  for (uint32_t n = 0; live; n++) {
    ml = ld_rlx2(pm);
    a0 = ld_rlx4(pa);
    a1 = ld_rlx4(pa + 16 * 128);
    uint32_t ml_stale = ((ml.x ^ tag) | (ml.y ^ tag)) & 7u;
    if (!__any_sync(0xffffffffu, ml_stale | stale4(a0, tag) | stale4(a1, tag))) break;
#pragma unroll 1
    while (live > 1 && __any_sync(0xffffffffu, ml_stale)) {
      __nanosleep(live);
      ml = ld_rlx2(pm);
      ml_stale = ((ml.x ^ tag) | (ml.y ^ tag)) & 7u;
      if (++n > kSpinLimit) __trap();
    }
    if (n > kSpinLimit) __trap();
  }
  float M = __uint_as_float(ml.x);
#pragma unroll
  for (int s = 16; s > 0; s >>= 1) M = fmaxf(M, __shfl_xor_sync(0xffffffffu, M, s));
  const float wa = ex2((__uint_as_float(ml.x) - M) * kScaleLog2);
  float L = wa * __uint_as_float(ml.y);
  const float w0 = __shfl_sync(0xffffffffu, wa, pg), w1 = __shfl_sync(0xffffffffu, wa, pg + 16);
  const float sx = w0 * __uint_as_float(a0.x) + w1 * __uint_as_float(a1.x);
  const float sy = w0 * __uint_as_float(a0.y) + w1 * __uint_as_float(a1.y);
  const float sz = w0 * __uint_as_float(a0.z) + w1 * __uint_as_float(a1.z);
  const float sw = w0 * __uint_as_float(a0.w) + w1 * __uint_as_float(a1.w);
  const bool u16 = lane & 16, u8 = lane & 8;
  const float ra = (u16 ? sz : sx) + __shfl_xor_sync(0xffffffffu, u16 ? sx : sz, 16);
  const float rb = (u16 ? sw : sy) + __shfl_xor_sync(0xffffffffu, u16 ? sy : sw, 16);
  const float r = (u8 ? rb : ra) + __shfl_xor_sync(0xffffffffu, u8 ? ra : rb, 8);
  sts32f(smem + kSmXs + lane * 16 + (tid >> 5) * 4, r);
#pragma unroll
  for (int s = 16; s > 0; s >>= 1) L += __shfl_xor_sync(0xffffffffu, L, s);
  glue_bar();
  const uint4 p = lds128(smem + kSmXs + lane * 16);
  const float o = __fdividef((__uint_as_float(p.x) + __uint_as_float(p.y)) + (__uint_as_float(p.z) + __uint_as_float(p.w)), L);
  const uint32_t t8 = (lane & 3) * 8;
#pragma unroll
  for (int k = 0; k < 4; k++)
    bo[k] = bf_pack(__shfl_sync(0xffffffffu, o, t8 + k), __shfl_sync(0xffffffffu, o, t8 + 4 + k));
}

__device__ __forceinline__ void mlp_hidden(uint32_t* bh, const float4 x, uint32_t smem) {
  const uint32_t tid = gtid(), ww = tid >> 5, lane = tid & 31;
  {
    const uint32_t a = smem + kSmXs + col0(tid) * 2;
    sts16(a, __float_as_uint(x.x) >> 16); sts16(a + 16, __float_as_uint(x.y) >> 16);
    sts16(a + 32, __float_as_uint(x.z) >> 16); sts16(a + 48, __float_as_uint(x.w) >> 16);
  }
  __syncwarp();
  float c[2][4];
#pragma unroll
  for (int k = 0; k < 4; k++) c[0][k] = c[1][k] = 0.f;
  const uint32_t wa = smem + kSmW1 + ((lane >> 3) & 1) * 8192 + (ww * 128 + (lane >> 4) * 8 + (lane & 7)) * 16;
  const uint32_t xa = smem + kSmXs + ww * 256 + (lane & 3) * 4;
  const bool odd = lane & 4;
#pragma unroll
  for (int ks = 0; ks < 8; ks += 2) {
    uint32_t a0[4], a1[4];
    ldsm4t(a0, wa + ks * 256);
    ldsm4t(a1, wa + ks * 256 + 256);
    const uint32_t b0 = lds32(xa + ks * 32), b1 = lds32(xa + ks * 32 + 16), b2 = lds32(xa + ks * 32 + 32), b3 = lds32(xa + ks * 32 + 48);
    mma16816(c[0], a0, odd ? kOnes : b0, odd ? kOnes : b1);
    mma16816(c[1], a1, odd ? kOnes : b2, odd ? kOnes : b3);
  }
  stats_put(x, smem);
  if ((lane & 3) == 0) {
    sts64(xa + 128 + (lane >> 2) * 8, __float_as_uint(c[0][0] + c[1][0]), __float_as_uint(c[0][1] + c[1][1]));
    sts64(xa + 192 + (lane >> 2) * 8, __float_as_uint(c[0][2] + c[1][2]), __float_as_uint(c[0][3] + c[1][3]));
  }
  uint32_t b1h;
  asm volatile("ld.shared.u16 %0, [%1];" : "=r"(b1h) : "r"(smem + kSmP + 32 + (lane & 15) * 2) : "memory");
  glue_bar();
  const uint32_t ha = smem + kSmXs + 128 + (lane & 15) * 8;
  const uint2 p0 = lds64(ha), p1 = lds64(ha + 256), p2 = lds64(ha + 512), p3 = lds64(ha + 768);
  const float2 st = stats_get(smem);
  const float dot = (__uint_as_float(p0.x) + __uint_as_float(p1.x)) + (__uint_as_float(p2.x) + __uint_as_float(p3.x));
  const float cs = (__uint_as_float(p0.y) + __uint_as_float(p1.y)) + (__uint_as_float(p2.y) + __uint_as_float(p3.y));
  const float hact = gelu_tanh(bf_round(bf_round(st.y * (dot - st.x * cs)) + bf_lo(b1h)));
  const uint32_t t4 = (lane & 3) * 4;
  bh[0] = bf_pack(__shfl_sync(0xffffffffu, hact, t4), __shfl_sync(0xffffffffu, hact, t4 + 2));
  bh[1] = bf_pack(__shfl_sync(0xffffffffu, hact, t4 + 1), __shfl_sync(0xffffffffu, hact, t4 + 3));
}

__device__ __forceinline__ void glue_role(const KParams& P, uint32_t smem, const uint32_t* xv, uint32_t epoch) {
  const uint2 x0 = make_uint2(xv[0] | (xv[1] << 16), xv[2] | (xv[3] << 16));
  const uint2 x1 = make_uint2(xv[4] | (xv[5] << 16), xv[6] | (xv[7] << 16));
  const uint32_t tag0 = ((epoch & 1) ^ 1) << 2;
  {
    const uint32_t tag = tag0;
    if (gtid() == 0) sts32f(smem + kSmTag, __uint_as_float(tag));
#pragma unroll 1
    for (uint32_t r = 0; r < 3; r++) {
      if (r == 1) mbar_wait(smem + kSmBar + kBarW * 8, 0);
      q_stage(unpack4(r == 2 ? x1 : x0), smem, r >> 1, r ? tag : tag ^ 4, r != 0);
      if (r && gtid() == 0) mbar_arrive(smem + kSmBar + (r == 2 ? kBarQ1 : kBarQ) * 8);
    }
  }
  {
    const uint32_t tid = gtid(), cta = gcta(), bar = smem + kSmBar + (kBarW + 1) * 8;
    const bool mlp = cta < kMlpCtas;
    if (tid == 0) mbar_expect(bar, mlp ? 49152 : 32768);
    if (tid < 8)
      bulk_load(smem + kSmWo + tid * (4096 + 16),
                P.wo + (size_t)(cta * 32 + tid * 4) * 512, 4096, bar, kPolFirst);
    else if (tid < 16 && mlp)
      bulk_load(smem + kSmW2 + (tid - 8) * (2048 + 16), P.w2 + (size_t)(cta * 16 + (tid - 8) * 2) * 512, 2048, bar, kPolFirst);
    if (tid >= 32 && tid < 44) {
      const uint32_t k = tid & 3, a = (tid - 32) >> 2;
      const bf16* src = a == 2 ? P.b2 : P.x + a * 512;
      sts16(smem + kSmP + (tid - 32) * 2, __bfloat16_as_ushort(src[col0(cta) + 8 * k]));
    }
    if (mlp) {
      if (tid >= 64 && tid < 66) cp16(smem + kSmP + 32 + (tid - 64) * 16, P.b1 + cta * 16 + (tid - 64) * 8);
      const bf16* src1 = P.w1 + (size_t)(tid >> 1) * 1792 + cta * 16 + (tid & 1) * 8;
#pragma unroll 1
      for (int i = 0; i < 8; i++) {
        uint4 v;
        asm volatile("ld.global.L1::no_allocate.L2::cache_hint.v4.b32 {%0,%1,%2,%3}, [%4], %5;"
                     : "=r"(v.x), "=r"(v.y), "=r"(v.z), "=r"(v.w) : "l"(src1 + (size_t)i * 64 * 1792), "l"(kPolFirst));
        asm volatile("st.shared.v4.b32 [%0], {%1,%2,%3,%4};" ::"r"(smem + kSmW1 + (tid & 1) * 8192 + (i * 64 + (tid >> 1)) * 16),
                     "r"(v.x), "r"(v.y), "r"(v.z), "r"(v.w) : "memory");
        asm volatile("cp.async.wait_all;" ::: "memory");
      }
    }
    mbar_wait(bar, 0);
  }

#pragma unroll 1
  for (uint32_t it = 0; it < 8; it++) {
    const uint32_t step = it >> 1;
    const uint32_t live = (it & 1) ? (it == 7 ? 1u : (it == 5 ? kPollGap2 : kPollGap)) : 0u;
    const uint32_t tag = tag0 ^ (((it & 1) ^ 1) << 2), ytag = tag | (step & 2);
    mbar_wait(smem + kSmBar + ((live ? kBarF : kBarP) + step) * 8, 0);
    {
      uint32_t bo[4];
      combine(bo, smem, step & 1, tag | (step >> 1), live);
      wide_mma<2>(smem + kSmWo, bo, step & 1, ytag);
    }
    {
      const float4 at = reduce_cols(step & 1, kCtas, smem, ytag, live);
      if (gtid() == 0) {
        const uint32_t xa = smem + kSmP + (step & 1) * 8;
        float4 x = unpack4(lds64(xa));
        x.x = bf_round(x.x + bf_round(at.x)); x.y = bf_round(x.y + bf_round(at.y));
        x.z = bf_round(x.z + bf_round(at.z)); x.w = bf_round(x.w + bf_round(at.w));
        st_rlx4(&g_x[step][0] + gcta() * 4, tagged(x.x, tag), tagged(x.y, tag), tagged(x.z, tag), tagged(x.w, tag));
        const uint2 xp = pack4(x);
        sts64(xa, xp.x, xp.y);
      }
    }
    if (gcta() < kMlpCtas) {
      const float4 x = poll_x(step, tag, live);
      uint32_t bh[2];
      mlp_hidden(bh, x, smem);
      wide_mma<1>(smem + kSmW2, bh, step & 1, ytag | 1);
    } else {
      glue_bar();
    }
    {
      const float4 mo = reduce_cols(step & 1, kMlpCtas, smem, ytag | 1, live);
      if (gtid() == 0) {
        const uint32_t xa = smem + kSmP + (step & 1) * 8;
        float4 x = unpack4(lds64(xa));
        const float4 b2 = unpack4(lds64(smem + kSmP + 16));
        x.x = bf_round(x.x + bf_round(bf_round(mo.x) + b2.x)); x.y = bf_round(x.y + bf_round(bf_round(mo.y) + b2.y));
        x.z = bf_round(x.z + bf_round(bf_round(mo.z) + b2.z)); x.w = bf_round(x.w + bf_round(bf_round(mo.w) + b2.w));
        const uint2 xp = pack4(x);
        if (step >= 2) {
          unsigned short* o = reinterpret_cast<unsigned short*>(P.out) + (step & 1) * 512 + col0(gcta());
          if (live) {
            o[0] = (unsigned short)xp.x; o[8] = (unsigned short)(xp.x >> 16);
            o[16] = (unsigned short)xp.y; o[24] = (unsigned short)(xp.y >> 16);
          }
        } else {
          st_rlx4(&g_x[4 + step][0] + gcta() * 4, tagged(x.x, tag), tagged(x.y, tag), tagged(x.z, tag), tagged(x.w, tag));
          if (live) sts64(xa, xp.x, xp.y);
        }
      }
    }
    if (step >= 2) continue;
    q_stage(poll_x(4 + step, tag, live), smem, 2 + step, tag, live);
    if (live && gtid() == 0) mbar_arrive(smem + kSmBar + (kBarQ + 1 + step) * 8);
  }
  if (gtid() == 0 && gcta() == 0) g_epoch = lds32(smem + kSmTag) >> 2;
}

__global__ void __launch_bounds__(kThreads, 1) fused_decode_kernel(const __grid_constant__ KParams P) {
  extern __shared__ __align__(1024) unsigned char smem_raw[];
  const uint32_t smem = (uint32_t)__cvta_generic_to_shared(smem_raw);
  uint32_t epoch = 0, xv[8] = {0, 0, 0, 0, 0, 0, 0, 0};
  if (threadIdx.x >= 256) {
    const uint32_t tid = threadIdx.x - 256, bar = smem + kSmBar + kBarW * 8;
    epoch = ld_rlx(&g_epoch);
#pragma unroll
    for (int i = 0; i < 8; i++)
      asm volatile("ld.global.nc.u16 %0, [%1];" : "=r"(xv[i]) : "l"(P.x + col0(tid) + (i >> 2) * 512 + (i & 3) * 8));
    if (tid == 0) {
      mbar_init(bar, 1);
      asm volatile("fence.mbarrier_init.release.cluster;" ::: "memory");
      mbar_expect(bar, 32768);
    }
    glue_bar();
    bulk_load(smem + kSmWq + tid * 256 + (tid >> 4) * 16,
              P.wq + (size_t)((blockIdx.x & 3) * 128 + tid) * 4096 + (blockIdx.x >> 2) * 128, 256, bar, kPolFirst);
  } else if ((threadIdx.x & 31) == 0) {
    const uint32_t w = threadIdx.x >> 5, bar = smem + kSmBar + w * kSlots * 8;
#pragma unroll
    for (int i = 0; i < kSlots; i++) mbar_init(bar + i * 8, 1);
    asm volatile("fence.mbarrier_init.release.cluster;" ::: "memory");
    mbar_expect(bar, kBlk);
    bulk_load(smem + w * kSlots * kBlk, (const char*)P.K + ((blockIdx.x << 19) + (w << 12)), kBlk, bar, kPolFirst);
  } else if (threadIdx.x >= kBarQ + 1 && threadIdx.x < kNumBars + 1 && threadIdx.x != kBarW + 1) {
    const uint32_t i = threadIdx.x - 1;
    mbar_init(smem + kSmBar + i * 8, (i >= kBarF && i < kBarW) ? 8 : 1);
    asm volatile("fence.mbarrier_init.release.cluster;" ::: "memory");
  }
  if (threadIdx.x == 97 || threadIdx.x == 98) asm volatile("prefetch.tensormap [%0];" ::"l"(&P.vmap[threadIdx.x - 97]) : "memory");
  if (threadIdx.x >= 65 && threadIdx.x < 71) sts32f(smem + kSmCnt + (threadIdx.x - 65) * 4, 0.f);
  __syncthreads();
  if (threadIdx.x < 256) {
    asm volatile("setmaxnreg.inc.sync.aligned.u32 %0;" ::"n"(kRegsMain));
    main_role(P, smem);
  } else {
    asm volatile("setmaxnreg.dec.sync.aligned.u32 %0;" ::"n"(kRegsGlue));
    glue_role(P, smem, xv, epoch);
  }
}

}

extern "C" void kernel_launch(void* const* d_in, const int* in_sizes, int n_in, void* d_out, int out_size) {
  (void)in_sizes; (void)n_in; (void)out_size;
  KParams P;
  P.x = (const bf16*)d_in[0];
  P.K = (const bf16*)d_in[1];
  P.V = (const bf16*)d_in[2];
  P.wq = (const bf16*)d_in[3];
  P.wo = (const bf16*)d_in[4];
  P.w1 = (const bf16*)d_in[6];
  P.b1 = (const bf16*)d_in[7];
  P.w2 = (const bf16*)d_in[8];
  P.b2 = (const bf16*)d_in[9];
  P.out = (bf16*)d_out;
  {
    typedef CUresult (*EncodeFn)(CUtensorMap*, CUtensorMapDataType, cuuint32_t, void*, const cuuint64_t*, const cuuint64_t*,
                                 const cuuint32_t*, const cuuint32_t*, CUtensorMapInterleave, CUtensorMapSwizzle,
                                 CUtensorMapL2promotion, CUtensorMapFloatOOBfill);
    static EncodeFn encode = nullptr;
    if (!encode) {
      cudaDriverEntryPointQueryResult qr;
      cudaGetDriverEntryPoint("cuTensorMapEncodeTiled", (void**)&encode, cudaEnableDefault, &qr);
    }
    const cuuint64_t dims[4] = {64, 16, 2, 2 * 32 * 512}, strides[3] = {256, 128, 4096};
    for (cuuint32_t i = 0; i < 2; i++) {
      const cuuint32_t box[4] = {64, 16, 2, i + 1}, estr[4] = {1, 1, 1, 1};
      encode(&P.vmap[i], CU_TENSOR_MAP_DATA_TYPE_BFLOAT16, 4, d_in[2], dims, strides, box, estr, CU_TENSOR_MAP_INTERLEAVE_NONE,
             CU_TENSOR_MAP_SWIZZLE_128B, CU_TENSOR_MAP_L2_PROMOTION_NONE, CU_TENSOR_MAP_FLOAT_OOB_FILL_NONE);
    }
  }
  for (uint32_t s = 0; s < 7; s++) {
    const uint32_t first = s == 2 ? 32 + 8 * kHeld : 32;
    const uint32_t n = s == 6 ? 0 : (s == 2 ? 48 - 4 * kHeld : (s == 4 ? 8 * kHeld : (s == 5 ? 48 : 96)));
    const uint32_t keep = s == 0 ? kKeep0 : (s == 3 ? 0 : 255);
    P.segp[s] = first | ((s == 5 || s == 2) << 15) | (s << 11) | ((s & 1) << 14) | (n << 16) | (keep << 24);
  }
  cudaFuncSetAttribute(fused_decode_kernel, cudaFuncAttributeMaxDynamicSharedMemorySize, kSmemBytes);
  fused_decode_kernel<<<kCtas, kThreads, kSmemBytes>>>(P);
}
```
